```python
import torch

def _softmax(x, axis=-1):
    return torch.softmax(x, dim=axis)

def _gelu(x):
    return torch.nn.functional.gelu(x, approximate='tanh')

def _silu(x):
    return torch.nn.functional.silu(x)

def _sigmoid(x):
    return torch.sigmoid(x)

def _layernorm(x, axis=-1, eps=1e-05):
    m = x.mean(dim=axis, keepdim=True)
    v = x.var(dim=axis, keepdim=True, unbiased=False)
    return (x - m) / torch.sqrt(v + eps)

def _scatter_add(tgt, idx, src, axis=0):
    return tgt.clone().index_add_(axis, idx, src)

def _segment_sum(src, seg, n):
    out = torch.zeros((n,) + src.shape[1:], dtype=src.dtype)
    return out.index_add_(0, seg, src)

def _pad(x, pw):
    flat = tuple((v for pair in reversed(pw) for v in pair))
    return torch.nn.functional.pad(x, flat)
kernel_name = 'recurrent_scan__softmax_full_mha__mixer_gmlp__prompt'

def setup_inputs():

    _w = lambda a: (lambda t: t.to(torch.bfloat16) if t.is_floating_point() else t)(torch.as_tensor(a))

    def _A_setup():
        B, S, D = (1, 2048, 512)
        return {'x': _w((lambda *s: torch.randn(*s, dtype=torch.bfloat16) * 0.05)(B, S, D)), 'wqkv': _w((lambda *s: torch.randn(*s, dtype=torch.bfloat16) * 0.05)(D, 3 * D)), 'wo': _w((lambda *s: torch.randn(*s, dtype=torch.bfloat16) * 0.05)(D, D))}
    _A_in = _A_setup()

    def _B_setup():
        B, S, D, F = (1, 2048, 512, 1792)
        Fh = F // 2
        return {'x': _w((lambda *s: torch.randn(*s, dtype=torch.bfloat16) * 0.05)(B, S, D)), 'w_in': _w((lambda *s: torch.randn(*s, dtype=torch.bfloat16) * 0.8)(D, 2 * Fh)), 'w_sp': _w(0.01 * (lambda *s: torch.randn(*s, dtype=torch.bfloat16) * 0.8)(S, S)), 'b_sp': _w(1.0 + 0.01 * (lambda *s: torch.randn(*s, dtype=torch.bfloat16) * 0.05)(S)), 'w_out': _w((lambda *s: torch.randn(*s, dtype=torch.bfloat16) * 0.05)(Fh, D))}
    _B_in = _B_setup()
    return {'A_x': _A_in['x'], 'A_wqkv': _A_in['wqkv'], 'A_wo': _A_in['wo'], 'B_x': _B_in['x'], 'B_w_in': _B_in['w_in'], 'B_w_sp': _B_in['w_sp'], 'B_b_sp': _B_in['b_sp'], 'B_w_out': _B_in['w_out']}

def reference(A_x, A_wqkv, A_wo, B_x, B_w_in, B_w_sp, B_b_sp, B_w_out):

    def _A_ref(x, wqkv, wo):
        B, S, D = x.shape
        H = 32
        Dh = D // H
        qkv = (lambda x, *d: x.permute(*d))((x @ wqkv).reshape(B, S, 3, H, Dh), 2, 0, 3, 1, 4)
        q, k, v = (qkv[0], qkv[1], qkv[2])
        scale = Dh ** (-0.5)
        scores = torch.einsum('bhqd,bhkd->bhqk', q, k) * scale
        p = _softmax(scores, axis=-1)
        o = torch.einsum('bhqk,bhkd->bhqd', p, v)
        return (lambda x, *d: x.permute(*d))(o, 0, 2, 1, 3).reshape(B, S, D) @ wo

    def _B_ref(x, w_in, w_sp, b_sp, w_out):
        B, S, D = x.shape
        F = w_in.shape[-1]
        Fh = F // 2
        z = _gelu(torch.einsum('bsd,df->bsf', x, w_in))
        z1 = z[..., :Fh].clone()
        z2 = _layernorm(z[..., Fh:], axis=-1)
        g = torch.einsum('ts,bsf->btf', w_sp, z2) + b_sp[None, :, None]
        return torch.einsum('bsf,fd->bsd', z1 * g, w_out)
    x = A_x
    xn = _layernorm(x, axis=-1)
    s = _A_ref(xn, A_wqkv, A_wo)
    g = _silu(_B_ref(xn, B_w_in, B_w_sp, B_b_sp, B_w_out))
    return x + s * g
```

```cpp
#include <cuda_runtime.h>
#include <cuda_bf16.h>
#include <cuda.h>
#include <stdint.h>

typedef __nv_bfloat16 bf16;

constexpr int S_ = 2048, D_ = 512, FH = 896;

__device__ __align__(1024) bf16 g_q[S_ * D_];
__device__ __align__(1024) bf16 g_k[S_ * D_];
__device__ __align__(1024) bf16 g_v[S_ * D_];
__device__ __align__(1024) bf16 g_o[S_ * D_];
__device__ __align__(1024) bf16 g_z1[S_ * FH];
__device__ __align__(1024) bf16 g_z2n[S_ * FH];
__device__ __align__(1024) float2 g_st[S_ * 8];
__device__ __align__(1024) bf16 g_u[S_ * FH];
__device__ __align__(128) float g_kh[128 * 128];
__device__ __align__(128) uint32_t g_kn[8 * 128 * 8];
__device__ __align__(128) float4 g_part[128 * 3 * 128];
__device__ __align__(128) uint32_t g_fq[128];
__device__ __align__(128) uint32_t g_fz[128];
__device__ uint32_t g_epoch;
__device__ __align__(128) uint32_t g_cnt[49 * 32];

#define WG_FENCE()  asm volatile("wgmma.fence.sync.aligned;" ::: "memory")
#define WG_COMMIT() asm volatile("wgmma.commit_group.sync.aligned;" ::: "memory")
#define WG_WAIT(n)  asm volatile("wgmma.wait_group.sync.aligned %0;" ::"n"(n) : "memory")

__device__ __forceinline__ uint32_t smem_u32(const void* p) { return (uint32_t)__cvta_generic_to_shared(p); }
__device__ __forceinline__ void mbar_init(uint32_t b, uint32_t cnt) { asm volatile("mbarrier.init.shared.b64 [%0], %1;" ::"r"(b), "r"(cnt)); }
__device__ __forceinline__ bool mbar_try(uint32_t b, uint32_t ph) {
  uint32_t ok;
  asm volatile("{\n.reg .pred p;\nmbarrier.try_wait.parity.shared.b64 p, [%1], %2;\nselp.b32 %0, 1, 0, p;\n}" : "=r"(ok) : "r"(b), "r"(ph) : "memory");
  return ok;
}
__device__ __forceinline__ void mbar_wait(uint32_t b, uint32_t ph) {
  #pragma unroll 1
  for (int i = 0; i < (1 << 22); i++) if (mbar_try(b, ph)) return;
  asm volatile("trap;");
}
__device__ __forceinline__ void mbar_wait_u(uint32_t b, uint32_t ph) {
  asm volatile("{\n.reg .pred p;\n.reg .u32 c;\nmov.u32 c, 0;\nL_%=:\nmbarrier.try_wait.parity.shared.b64 p, [%0], %1;\n"
               "vote.sync.all.pred p, p, 0xffffffff;\n@p bra.uni D_%=;\nadd.u32 c, c, 1;\nsetp.lt.u32 p, c, 4194304;\n@p bra.uni L_%=;\ntrap;\nD_%=:\n}"
               ::"r"(b), "r"(ph) : "memory");
}
__device__ __forceinline__ void mbar_arrive(uint32_t b) { asm volatile("mbarrier.arrive.shared.b64 _, [%0];" ::"r"(b) : "memory"); }
__device__ __forceinline__ void mbar_expect(uint32_t b, uint32_t bytes) { asm volatile("mbarrier.arrive.expect_tx.shared.b64 _, [%0], %1;" ::"r"(b), "r"(bytes) : "memory"); }
__device__ __forceinline__ void tma2d(uint32_t dst, const CUtensorMap* m, int c0, int c1, uint32_t bar) {
  asm volatile("cp.async.bulk.tensor.2d.shared::cluster.global.mbarrier::complete_tx::bytes [%0], [%1, {%3, %4}], [%2];"
               ::"r"(dst), "l"(m), "r"(bar), "r"(c0), "r"(c1) : "memory");
}
__device__ __forceinline__ void tma2d_e(uint32_t dst, const CUtensorMap* m, int c0, int c1, uint32_t bar) {
  asm volatile("{\n.reg .pred p;\nelect.sync _|p, 0xffffffff;\n"
               "@p cp.async.bulk.tensor.2d.shared::cluster.global.mbarrier::complete_tx::bytes [%0], [%1, {%3, %4}], [%2];\n}"
               ::"r"(dst), "l"(m), "r"(bar), "r"(c0), "r"(c1) : "memory");
}
__device__ __forceinline__ void tma3d_e(uint32_t dst, const CUtensorMap* m, int c0, int c1, int c2, uint32_t bar) {
  asm volatile("{\n.reg .pred p;\nelect.sync _|p, 0xffffffff;\n"
               "@p cp.async.bulk.tensor.3d.shared::cluster.global.mbarrier::complete_tx::bytes [%0], [%1, {%3, %4, %5}], [%2];\n}"
               ::"r"(dst), "l"(m), "r"(bar), "r"(c0), "r"(c1), "r"(c2) : "memory");
}
__device__ __forceinline__ void mbar_expect_e(uint32_t b, uint32_t bytes) {
  asm volatile("{\n.reg .pred p;\nelect.sync _|p, 0xffffffff;\n@p mbarrier.arrive.expect_tx.shared.b64 _, [%0], %1;\n}" ::"r"(b), "r"(bytes) : "memory");
}
__device__ __forceinline__ void mbar_arrive_e(uint32_t b) {
  asm volatile("{\n.reg .pred p;\nelect.sync _|p, 0xffffffff;\n@p mbarrier.arrive.shared.b64 _, [%0];\n}" ::"r"(b) : "memory");
}
__device__ __forceinline__ void bulk1d(uint32_t dst, const void* src, uint32_t bytes, uint32_t bar) {
  asm volatile("cp.async.bulk.shared::cluster.global.mbarrier::complete_tx::bytes [%0], [%1], %2, [%3];" ::"r"(dst), "l"(src), "r"(bytes), "r"(bar) : "memory");
}
__device__ __forceinline__ void tma2d_store(const CUtensorMap* m, uint32_t src, int c0, int c1) {
  asm volatile("cp.async.bulk.tensor.2d.global.shared::cta.bulk_group [%0, {%2, %3}], [%1];" ::"l"(m), "r"(src), "r"(c0), "r"(c1) : "memory");
}
__device__ __forceinline__ void l2_prefetch(const void* p, uint32_t bytes) {
  asm volatile("cp.async.bulk.prefetch.L2.global [%0], %1;" ::"l"(p), "r"(bytes) : "memory");
}
__device__ __forceinline__ void ldsm4(uint32_t& a, uint32_t& b, uint32_t& c, uint32_t& d, uint32_t addr) {
  asm volatile("ldmatrix.sync.aligned.m8n8.x4.shared.b16 {%0,%1,%2,%3}, [%4];" : "=r"(a), "=r"(b), "=r"(c), "=r"(d) : "r"(addr) : "memory");
}
__device__ __forceinline__ void stsm4(uint32_t addr, uint32_t a, uint32_t b, uint32_t c, uint32_t d) {
  asm volatile("stmatrix.sync.aligned.m8n8.x4.shared.b16 [%0], {%1,%2,%3,%4};" ::"r"(addr), "r"(a), "r"(b), "r"(c), "r"(d) : "memory");
}
__device__ __forceinline__ void mma16816(float (&c)[4], uint32_t a0, uint32_t a1, uint32_t a2, uint32_t a3, uint32_t b0, uint32_t b1) {
  asm("mma.sync.aligned.m16n8k16.row.col.f32.bf16.bf16.f32 {%0,%1,%2,%3}, {%4,%5,%6,%7}, {%8,%9}, {%0,%1,%2,%3};"
      : "+f"(c[0]), "+f"(c[1]), "+f"(c[2]), "+f"(c[3]) : "r"(a0), "r"(a1), "r"(a2), "r"(a3), "r"(b0), "r"(b1));
}
__device__ __forceinline__ uint32_t hsub2_bf(uint32_t a, uint32_t b) { uint32_t r; asm("sub.rn.bf16x2 %0, %1, %2;" : "=r"(r) : "r"(a), "r"(b)); return r; }
__device__ __forceinline__ uint32_t hmul2_bf(uint32_t a, uint32_t b) { uint32_t r; asm("mul.rn.bf16x2 %0, %1, %2;" : "=r"(r) : "r"(a), "r"(b)); return r; }
__device__ __forceinline__ uint32_t hfma2_bf(uint32_t a, uint32_t b, uint32_t c) { uint32_t r; asm("fma.rn.bf16x2 %0, %1, %2, %3;" : "=r"(r) : "r"(a), "r"(b), "r"(c)); return r; }
__device__ __forceinline__ void flag_add(uint32_t* p) {
  asm volatile("fence.proxy.async.global;" ::: "memory");
  asm volatile("red.release.gpu.global.add.u32 [%0], 1;" ::"l"(p) : "memory");
}
__device__ __forceinline__ void flag_wait(const uint32_t* p, uint32_t target) {
  #pragma unroll 1
  for (int i = 0; i < (1 << 22); i++) {
    uint32_t v;
    asm volatile("ld.acquire.gpu.global.u32 %0, [%1];" : "=r"(v) : "l"(p) : "memory");
    if ((int)(v - target) >= 0) { asm volatile("fence.proxy.async.global;" ::: "memory"); return; }
  }
  asm volatile("trap;");
}
__device__ __forceinline__ void flag_set(uint32_t* p, uint32_t v) {
  asm volatile("fence.proxy.async.global;" ::: "memory");
  asm volatile("st.release.gpu.global.u32 [%0], %1;" ::"l"(p), "r"(v) : "memory");
}
template <int N>
__device__ __forceinline__ void flags_wait_warp(const uint32_t* p, uint32_t tag, int lane) {
  #pragma unroll 1
  for (int i = 0; i < (1 << 22); i++) {
    uint32_t a = tag, b = tag, c = tag, d = tag;
    if (N == 128 || lane < N / 4)
      asm volatile("ld.acquire.gpu.global.v4.u32 {%0,%1,%2,%3}, [%4];" : "=r"(a), "=r"(b), "=r"(c), "=r"(d) : "l"(p + 4 * lane) : "memory");
    if (__all_sync(0xffffffffu, a == tag && b == tag && c == tag && d == tag)) break;
    __nanosleep(32);
  }
  __syncwarp();
  asm volatile("fence.proxy.async.global;" ::: "memory");
}
template <int N> __device__ __forceinline__ void fence_regs(float (&d)[N]) {
  #pragma unroll
  for (int i = 0; i < N; i++) asm volatile("" : "+f"(d[i])::"memory");
}
template <int N> __device__ __forceinline__ void fence_regs(uint32_t (&d)[N]) {
  #pragma unroll
  for (int i = 0; i < N; i++) asm volatile("" : "+r"(d[i])::"memory");
}
__device__ __forceinline__ uint32_t pack_bf16(float lo, float hi) {
  uint32_t r; asm("cvt.rn.bf16x2.f32 %0, %1, %2;" : "=r"(r) : "f"(hi), "f"(lo)); return r;
}
__device__ __forceinline__ float bf_lo(uint32_t v) { return __uint_as_float(v << 16); }
__device__ __forceinline__ float bf_hi(uint32_t v) { return __uint_as_float(v & 0xffff0000u); }
__device__ __forceinline__ float round_bf(float x) { return __bfloat162float(__float2bfloat16_rn(x)); }
__device__ __forceinline__ float ex2f(float x) { float y; asm("ex2.approx.ftz.f32 %0, %1;" : "=f"(y) : "f"(x)); return y; }
__device__ __forceinline__ float rcpf(float x) { float y; asm("rcp.approx.ftz.f32 %0, %1;" : "=f"(y) : "f"(x)); return y; }
__device__ __forceinline__ float rstd_bf(float var) {
  float t;
  asm("sqrt.approx.ftz.f32 %0, %1;" : "=f"(t) : "f"(round_bf(round_bf(var) + 1e-5f)));
  return rcpf(round_bf(t));
}
__device__ __forceinline__ float gelu2(float a, float k1, float k3) {
  float y = a * fmaf(a * a, k3, k1), t;
  asm("tanh.approx.f32 %0, %1;" : "=f"(t) : "f"(y));
  return fmaf(a, t, a);
}

__device__ __forceinline__ void wgmma_ss_n96(float (&d)[48], uint64_t da, uint64_t db, int sd) {
  asm volatile("{\n.reg .pred p;\nsetp.ne.b32 p, %50, 0;\n"
    "wgmma.mma_async.sync.aligned.m64n96k16.f32.bf16.bf16 {%0,%1,%2,%3,%4,%5,%6,%7,%8,%9,%10,%11,%12,%13,%14,%15,%16,%17,%18,%19,%20,%21,%22,%23,%24,%25,%26,%27,%28,%29,%30,%31,%32,%33,%34,%35,%36,%37,%38,%39,%40,%41,%42,%43,%44,%45,%46,%47}, %48, %49, p, 1, 1, 0, 1;\n}\n"
    : "+f"(d[0]), "+f"(d[1]), "+f"(d[2]), "+f"(d[3]), "+f"(d[4]), "+f"(d[5]), "+f"(d[6]), "+f"(d[7]),
      "+f"(d[8]), "+f"(d[9]), "+f"(d[10]), "+f"(d[11]), "+f"(d[12]), "+f"(d[13]), "+f"(d[14]), "+f"(d[15]),
      "+f"(d[16]), "+f"(d[17]), "+f"(d[18]), "+f"(d[19]), "+f"(d[20]), "+f"(d[21]), "+f"(d[22]), "+f"(d[23]),
      "+f"(d[24]), "+f"(d[25]), "+f"(d[26]), "+f"(d[27]), "+f"(d[28]), "+f"(d[29]), "+f"(d[30]), "+f"(d[31]),
      "+f"(d[32]), "+f"(d[33]), "+f"(d[34]), "+f"(d[35]), "+f"(d[36]), "+f"(d[37]), "+f"(d[38]), "+f"(d[39]),
      "+f"(d[40]), "+f"(d[41]), "+f"(d[42]), "+f"(d[43]), "+f"(d[44]), "+f"(d[45]), "+f"(d[46]), "+f"(d[47])
    : "l"(da), "l"(db), "r"(sd));
}
__device__ __forceinline__ void wgmma_ss_n112(float (&d)[56], uint64_t da, uint64_t db, int sd) {
  asm volatile("{\n.reg .pred p;\nsetp.ne.b32 p, %58, 0;\n"
    "wgmma.mma_async.sync.aligned.m64n112k16.f32.bf16.bf16 {%0,%1,%2,%3,%4,%5,%6,%7,%8,%9,%10,%11,%12,%13,%14,%15,%16,%17,%18,%19,%20,%21,%22,%23,%24,%25,%26,%27,%28,%29,%30,%31,%32,%33,%34,%35,%36,%37,%38,%39,%40,%41,%42,%43,%44,%45,%46,%47,%48,%49,%50,%51,%52,%53,%54,%55}, %56, %57, p, 1, 1, 0, 1;\n}\n"
    : "+f"(d[0]), "+f"(d[1]), "+f"(d[2]), "+f"(d[3]), "+f"(d[4]), "+f"(d[5]), "+f"(d[6]), "+f"(d[7]),
      "+f"(d[8]), "+f"(d[9]), "+f"(d[10]), "+f"(d[11]), "+f"(d[12]), "+f"(d[13]), "+f"(d[14]), "+f"(d[15]),
      "+f"(d[16]), "+f"(d[17]), "+f"(d[18]), "+f"(d[19]), "+f"(d[20]), "+f"(d[21]), "+f"(d[22]), "+f"(d[23]),
      "+f"(d[24]), "+f"(d[25]), "+f"(d[26]), "+f"(d[27]), "+f"(d[28]), "+f"(d[29]), "+f"(d[30]), "+f"(d[31]),
      "+f"(d[32]), "+f"(d[33]), "+f"(d[34]), "+f"(d[35]), "+f"(d[36]), "+f"(d[37]), "+f"(d[38]), "+f"(d[39]),
      "+f"(d[40]), "+f"(d[41]), "+f"(d[42]), "+f"(d[43]), "+f"(d[44]), "+f"(d[45]), "+f"(d[46]), "+f"(d[47]),
      "+f"(d[48]), "+f"(d[49]), "+f"(d[50]), "+f"(d[51]), "+f"(d[52]), "+f"(d[53]), "+f"(d[54]), "+f"(d[55])
    : "l"(da), "l"(db), "r"(sd));
}
__device__ __forceinline__ void wgmma_ss_n128(float (&d)[64], uint64_t da, uint64_t db, int sd) {
  asm volatile("{\n.reg .pred p;\nsetp.ne.b32 p, %66, 0;\n"
    "wgmma.mma_async.sync.aligned.m64n128k16.f32.bf16.bf16 {%0,%1,%2,%3,%4,%5,%6,%7,%8,%9,%10,%11,%12,%13,%14,%15,%16,%17,%18,%19,%20,%21,%22,%23,%24,%25,%26,%27,%28,%29,%30,%31,%32,%33,%34,%35,%36,%37,%38,%39,%40,%41,%42,%43,%44,%45,%46,%47,%48,%49,%50,%51,%52,%53,%54,%55,%56,%57,%58,%59,%60,%61,%62,%63}, %64, %65, p, 1, 1, 0, 1;\n}\n"
    : "+f"(d[0]), "+f"(d[1]), "+f"(d[2]), "+f"(d[3]), "+f"(d[4]), "+f"(d[5]), "+f"(d[6]), "+f"(d[7]),
      "+f"(d[8]), "+f"(d[9]), "+f"(d[10]), "+f"(d[11]), "+f"(d[12]), "+f"(d[13]), "+f"(d[14]), "+f"(d[15]),
      "+f"(d[16]), "+f"(d[17]), "+f"(d[18]), "+f"(d[19]), "+f"(d[20]), "+f"(d[21]), "+f"(d[22]), "+f"(d[23]),
      "+f"(d[24]), "+f"(d[25]), "+f"(d[26]), "+f"(d[27]), "+f"(d[28]), "+f"(d[29]), "+f"(d[30]), "+f"(d[31]),
      "+f"(d[32]), "+f"(d[33]), "+f"(d[34]), "+f"(d[35]), "+f"(d[36]), "+f"(d[37]), "+f"(d[38]), "+f"(d[39]),
      "+f"(d[40]), "+f"(d[41]), "+f"(d[42]), "+f"(d[43]), "+f"(d[44]), "+f"(d[45]), "+f"(d[46]), "+f"(d[47]),
      "+f"(d[48]), "+f"(d[49]), "+f"(d[50]), "+f"(d[51]), "+f"(d[52]), "+f"(d[53]), "+f"(d[54]), "+f"(d[55]),
      "+f"(d[56]), "+f"(d[57]), "+f"(d[58]), "+f"(d[59]), "+f"(d[60]), "+f"(d[61]), "+f"(d[62]), "+f"(d[63])
    : "l"(da), "l"(db), "r"(sd));
}
__device__ __forceinline__ void wgmma_ss_n192(float (&d)[96], uint64_t da, uint64_t db, int sd) {
  asm volatile("{\n.reg .pred p;\nsetp.ne.b32 p, %98, 0;\n"
    "wgmma.mma_async.sync.aligned.m64n192k16.f32.bf16.bf16 {%0,%1,%2,%3,%4,%5,%6,%7,%8,%9,%10,%11,%12,%13,%14,%15,%16,%17,%18,%19,%20,%21,%22,%23,%24,%25,%26,%27,%28,%29,%30,%31,%32,%33,%34,%35,%36,%37,%38,%39,%40,%41,%42,%43,%44,%45,%46,%47,%48,%49,%50,%51,%52,%53,%54,%55,%56,%57,%58,%59,%60,%61,%62,%63,%64,%65,%66,%67,%68,%69,%70,%71,%72,%73,%74,%75,%76,%77,%78,%79,%80,%81,%82,%83,%84,%85,%86,%87,%88,%89,%90,%91,%92,%93,%94,%95}, %96, %97, p, 1, 1, 0, 1;\n}\n"
    : "+f"(d[0]), "+f"(d[1]), "+f"(d[2]), "+f"(d[3]), "+f"(d[4]), "+f"(d[5]), "+f"(d[6]), "+f"(d[7]),
      "+f"(d[8]), "+f"(d[9]), "+f"(d[10]), "+f"(d[11]), "+f"(d[12]), "+f"(d[13]), "+f"(d[14]), "+f"(d[15]),
      "+f"(d[16]), "+f"(d[17]), "+f"(d[18]), "+f"(d[19]), "+f"(d[20]), "+f"(d[21]), "+f"(d[22]), "+f"(d[23]),
      "+f"(d[24]), "+f"(d[25]), "+f"(d[26]), "+f"(d[27]), "+f"(d[28]), "+f"(d[29]), "+f"(d[30]), "+f"(d[31]),
      "+f"(d[32]), "+f"(d[33]), "+f"(d[34]), "+f"(d[35]), "+f"(d[36]), "+f"(d[37]), "+f"(d[38]), "+f"(d[39]),
      "+f"(d[40]), "+f"(d[41]), "+f"(d[42]), "+f"(d[43]), "+f"(d[44]), "+f"(d[45]), "+f"(d[46]), "+f"(d[47]),
      "+f"(d[48]), "+f"(d[49]), "+f"(d[50]), "+f"(d[51]), "+f"(d[52]), "+f"(d[53]), "+f"(d[54]), "+f"(d[55]),
      "+f"(d[56]), "+f"(d[57]), "+f"(d[58]), "+f"(d[59]), "+f"(d[60]), "+f"(d[61]), "+f"(d[62]), "+f"(d[63]),
      "+f"(d[64]), "+f"(d[65]), "+f"(d[66]), "+f"(d[67]), "+f"(d[68]), "+f"(d[69]), "+f"(d[70]), "+f"(d[71]),
      "+f"(d[72]), "+f"(d[73]), "+f"(d[74]), "+f"(d[75]), "+f"(d[76]), "+f"(d[77]), "+f"(d[78]), "+f"(d[79]),
      "+f"(d[80]), "+f"(d[81]), "+f"(d[82]), "+f"(d[83]), "+f"(d[84]), "+f"(d[85]), "+f"(d[86]), "+f"(d[87]),
      "+f"(d[88]), "+f"(d[89]), "+f"(d[90]), "+f"(d[91]), "+f"(d[92]), "+f"(d[93]), "+f"(d[94]), "+f"(d[95])
    : "l"(da), "l"(db), "r"(sd));
}


__device__ __forceinline__ void wgmma_qk(float (&d)[32], const uint32_t (&a)[4], uint64_t db) {
  asm volatile("wgmma.mma_async.sync.aligned.m64n64k16.f32.bf16.bf16 {%0,%1,%2,%3,%4,%5,%6,%7,%8,%9,%10,%11,%12,%13,%14,%15,%16,%17,%18,%19,%20,%21,%22,%23,%24,%25,%26,%27,%28,%29,%30,%31}, {%32,%33,%34,%35}, %36, 0, 1, 1, 0;\n"
    : "+f"(d[0]), "+f"(d[1]), "+f"(d[2]), "+f"(d[3]), "+f"(d[4]), "+f"(d[5]), "+f"(d[6]), "+f"(d[7]),
      "+f"(d[8]), "+f"(d[9]), "+f"(d[10]), "+f"(d[11]), "+f"(d[12]), "+f"(d[13]), "+f"(d[14]), "+f"(d[15]),
      "+f"(d[16]), "+f"(d[17]), "+f"(d[18]), "+f"(d[19]), "+f"(d[20]), "+f"(d[21]), "+f"(d[22]), "+f"(d[23]),
      "+f"(d[24]), "+f"(d[25]), "+f"(d[26]), "+f"(d[27]), "+f"(d[28]), "+f"(d[29]), "+f"(d[30]), "+f"(d[31])
    : "r"(a[0]), "r"(a[1]), "r"(a[2]), "r"(a[3]), "l"(db));
}
__device__ __forceinline__ void wgmma_qk_acc(float (&d)[20], const uint32_t (&a)[4], uint64_t db) {
  asm volatile("wgmma.mma_async.sync.aligned.m64n40k16.f32.bf16.bf16 {%0,%1,%2,%3,%4,%5,%6,%7,%8,%9,%10,%11,%12,%13,%14,%15,%16,%17,%18,%19}, {%20,%21,%22,%23}, %24, 1, 1, 1, 0;\n"
    : "+f"(d[0]), "+f"(d[1]), "+f"(d[2]), "+f"(d[3]), "+f"(d[4]), "+f"(d[5]), "+f"(d[6]), "+f"(d[7]),
      "+f"(d[8]), "+f"(d[9]), "+f"(d[10]), "+f"(d[11]), "+f"(d[12]), "+f"(d[13]), "+f"(d[14]), "+f"(d[15]),
      "+f"(d[16]), "+f"(d[17]), "+f"(d[18]), "+f"(d[19])
    : "r"(a[0]), "r"(a[1]), "r"(a[2]), "r"(a[3]), "l"(db));
}
__device__ __forceinline__ void wgmma_qk(float (&d)[12], const uint32_t (&a)[4], uint64_t db) {
  asm volatile("wgmma.mma_async.sync.aligned.m64n24k16.f32.bf16.bf16 {%0,%1,%2,%3,%4,%5,%6,%7,%8,%9,%10,%11}, {%12,%13,%14,%15}, %16, 0, 1, 1, 0;\n"
    : "+f"(d[0]), "+f"(d[1]), "+f"(d[2]), "+f"(d[3]), "+f"(d[4]), "+f"(d[5]), "+f"(d[6]), "+f"(d[7]),
      "+f"(d[8]), "+f"(d[9]), "+f"(d[10]), "+f"(d[11])
    : "r"(a[0]), "r"(a[1]), "r"(a[2]), "r"(a[3]), "l"(db));
}
__device__ __forceinline__ void wgmma_pv(float (&d)[12], uint32_t a0, uint32_t a1, uint32_t a2, uint32_t a3, uint64_t db) {
  asm volatile("wgmma.mma_async.sync.aligned.m64n24k16.f32.bf16.bf16 {%0,%1,%2,%3,%4,%5,%6,%7,%8,%9,%10,%11}, {%12,%13,%14,%15}, %16, 1, 1, 1, 1;\n"
    : "+f"(d[0]), "+f"(d[1]), "+f"(d[2]), "+f"(d[3]), "+f"(d[4]), "+f"(d[5]), "+f"(d[6]), "+f"(d[7]),
      "+f"(d[8]), "+f"(d[9]), "+f"(d[10]), "+f"(d[11])
    : "r"(a0), "r"(a1), "r"(a2), "r"(a3), "l"(db));
}
template <int BN> __device__ __forceinline__ void wgmma_ss(float (&d)[BN / 2], uint64_t da, uint64_t db, int sd) {
  if constexpr (BN == 112) wgmma_ss_n112(d, da, db, sd);
  if constexpr (BN == 192) wgmma_ss_n192(d, da, db, sd);
  if constexpr (BN == 128) wgmma_ss_n128(d, da, db, sd);
  if constexpr (BN == 96) wgmma_ss_n96(d, da, db, sd);
}

constexpr int RING = 131072, ST = 3, SB = 32768, AT_V = 65536, P1S = 7, P1B = 14336  , AT_ONES = RING + P1S * P1B, BAR = AT_ONES + 512, SMEM = BAR + 512;
constexpr int B_FULL = BAR + 384, B_EMPTY = BAR + 448, B_X = BAR + 64, B_KV = BAR + 128, B_FULL2 = BAR + 168, B_ADONE = BAR + 216, B_GUARD = BAR + 224, B_TAG = BAR + 228, B_BIAS = BAR + 240, B_FULL3 = BAR + 256, B_WOB = BAR + 288, B_KVFREE = BAR + 296, B_GRD = BAR + 304;
constexpr int SB3 = 24576;
struct Maps { CUtensorMap win4, win3, wqkv, x128, wsp, z2n, z1, u, wout, o, wo, x, out; };
__device__ __forceinline__ uint64_t desc_a(uint32_t addr) { return ((uint64_t)1 << 16) | ((uint64_t)64 << 32) | ((uint64_t)1 << 62) | (uint64_t)((addr & 0x3FFFF) >> 4); }
__device__ __forceinline__ uint64_t desc_b(uint32_t addr) { return ((uint64_t)512 << 16) | ((uint64_t)64 << 32) | ((uint64_t)1 << 62) | (uint64_t)((addr & 0x3FFFF) >> 4); }

__device__ __forceinline__ void first_q(uint32_t sb, int tid, int wg, uint32_t (&qn)[4]) {
  mbar_wait_u(sb + B_GRD, 0);
  const int lane = tid & 31, row = (blockIdx.x & 3) * 512 + (((wg == 0 ? 7 : 2 - wg) + (blockIdx.x >> 4)) & 7) * 64 + ((tid >> 5) & 3) * 16 + (lane >> 2);
  const uint32_t* p = (const uint32_t*)(g_q + ((size_t)(blockIdx.x >> 2) * S_ + row) * 16) + (lane & 3);
  qn[0] = __ldcg(p); qn[1] = __ldcg(p + 64); qn[2] = __ldcg(p + 4); qn[3] = __ldcg(p + 68);
}
__device__ __forceinline__ void phase1(uint32_t sb, int tid, int wg, int mb, int nb, uint32_t (&qn)[4]) {
    const int lane = tid & 31;
    const uint32_t full = sb + B_FULL, empty = sb + B_EMPTY, xbar = sb + B_X;
    const int n2 = 4 - (nb & 1), a2 = (7 * nb + 1) >> 1, a1 = (7 * nb) >> 1;
    const int warp = (tid >> 5) & 3, q = lane & 3, r = lane >> 2;
    const int lr = wg * 64 + warp * 16 + r;
    const int r0 = mb * 128 + lr;
    const uint32_t xa = sb + (wg * 64 + warp * 16 + (lane & 7) + ((lane >> 3) & 1) * 8) * 128;
    const uint32_t xsw = ((lane >> 4) ^ (lane & 7)) << 4;
    float cs[4] = {0.f, 0.f, 0.f, 0.f}, c0[4] = {0.f, 0.f, 0.f, 0.f}, c1[4] = {0.f, 0.f, 0.f, 0.f};
    uint32_t v[32][4];
    #pragma unroll
    for (int i = 0; i < 32; i++) {
      if ((i & 3) == 0) mbar_wait(xbar + 8 * (i >> 2), 0);
      ldsm4(v[i][0], v[i][1], v[i][2], v[i][3], xa + (i >> 2) * 16384 + (xsw ^ ((i & 3) << 5)));
      mma16816(cs, v[i][0], v[i][1], v[i][2], v[i][3], 0x3F803F80u, 0x3F803F80u);
      mma16816(c0, v[i][0], v[i][1], v[i][2], v[i][3], v[i][0], v[i][2]);
      mma16816(c1, v[i][0], v[i][1], v[i][2], v[i][3], v[i][1], v[i][3]);
    }
    const float mean0 = cs[0] * (1.f / D_), mean1 = cs[2] * (1.f / D_);
    const uint32_t m0 = pack_bf16(mean0, mean0), m1 = pack_bf16(mean1, mean1);
    #pragma unroll
    for (int i = 0; i < 32; i++)
      stsm4(xa + (i >> 2) * 16384 + (xsw ^ ((i & 3) << 5)), hsub2_bf(v[i][0], m0), hsub2_bf(v[i][1], m1), hsub2_bf(v[i][2], m0), hsub2_bf(v[i][3], m1));
    asm volatile("fence.proxy.async.shared::cta;" ::: "memory");
    if (wg == 0) asm volatile("bar.sync 1, 128;" ::: "memory"); else asm volatile("bar.sync 2, 128;" ::: "memory");
    float aq[96];
    const uint64_t dA = desc_a(sb + wg * 8192);
    const uint64_t dB = ((uint64_t)256 << 16) | ((uint64_t)64 << 32) | ((uint64_t)1 << 62) | (uint64_t)(((sb + RING) & 0x3FFFF) >> 4);
    const uint64_t dZ = ((uint64_t)128 << 16) | ((uint64_t)32 << 32) | ((uint64_t)2 << 62) | (uint64_t)(((sb + RING) & 0x3FFFF) >> 4);
    int s = 0, prev = 0; uint32_t ph = 0;
    #pragma unroll 1
    for (int k = 0; k < 16; k++) {
      mbar_wait(full + 8 * s, ph);
      WG_FENCE();
      #pragma unroll
      for (int j = 0; j < 2; j++) wgmma_ss<192>(aq, dA + (k >> 1) * 1024 + (k & 1) * 4 + j * 2, dB + s * (P1B >> 4) + j * 128, (k | j) != 0);
      WG_COMMIT();
      WG_WAIT(1);
      if (k > 0) mbar_arrive_e(empty + 8 * prev);
      prev = s;
      if (++s == P1S) { s = 0; ph ^= 1; }
    }
    float rs0, rs1;
    {
      const int src = (lane & ~3) | (r >> 1);
      float q0 = __shfl_sync(0xffffffffu, (r & 1) ? c0[1] : c0[0], src), q1 = __shfl_sync(0xffffffffu, (r & 1) ? c1[3] : c1[2], src);
      float var0 = q0 * (1.f / D_) - mean0 * mean0, var1 = q1 * (1.f / D_) - mean1 * mean1;
      if (__any_sync(0xffffffffu, !(var0 * 64.f >= mean0 * mean0) || !(var1 * 64.f >= mean1 * mean1))) {
        #pragma unroll
        for (int j = 0; j < 4; j++) { c0[j] = 0.f; c1[j] = 0.f; }
        #pragma unroll 1
        for (int i = 0; i < 32; i++) {
          uint32_t w0, w1, w2, w3;
          ldsm4(w0, w1, w2, w3, xa + (i >> 2) * 16384 + (xsw ^ ((i & 3) << 5)));
          mma16816(c0, w0, w1, w2, w3, w0, w2);
          mma16816(c1, w0, w1, w2, w3, w1, w3);
        }
        q0 = __shfl_sync(0xffffffffu, (r & 1) ? c0[1] : c0[0], src); q1 = __shfl_sync(0xffffffffu, (r & 1) ? c1[3] : c1[2], src);
        const float e0 = mean0 - bf_lo(m0), e1 = mean1 - bf_lo(m1);
        var0 = fmaxf(q0 * (1.f / D_) - e0 * e0, 0.f); var1 = fmaxf(q1 * (1.f / D_) - e1 * e1, 0.f);
      }
      rs0 = rstd_bf(var0); rs1 = rstd_bf(var1);
    }
    WG_WAIT(0);
    fence_regs(aq);
    mbar_arrive_e(empty + 8 * prev);
    float za[64], zb[48];
    uint32_t pq[48];
    #pragma unroll
    for (int i = 0; i < 48; i++) {
      const float sc = ((i & 1) ? rs1 : rs0) * (i < 16 ? 0.25f * 1.4426950408889634f : 1.f);
      pq[i] = pack_bf16(aq[2 * i] * sc, aq[2 * i + 1] * sc);
    }
    fence_regs(pq);
    uint32_t mine = 0;
    #pragma unroll
    for (int k = 0; k < 16; k++) {
      mbar_wait(full + 8 * s, ph);
      WG_FENCE();
      #pragma unroll
      for (int j = 0; j < 2; j++) {
        wgmma_ss<128>(za, dA + (k >> 1) * 1024 + (k & 1) * 4 + j * 2, dZ + s * (P1B >> 4) + j * 64, (k | j) != 0);
        wgmma_ss<96>(zb, dA + (k >> 1) * 1024 + (k & 1) * 4 + j * 2, dZ + s * (P1B >> 4) + 512 + j * 64, (k | j) != 0);
      }
      WG_COMMIT();
      if (k > 0 && k <= 16 - P1S) { WG_WAIT(1); mbar_arrive_e(empty + 8 * prev); }
      prev = s;
      if (++s == P1S) { s = 0; ph ^= 1; }
      #pragma unroll
      for (int c = 0; c < 24; c++) {
        if (c / 2 == k) {
          const int b = c >> 3, e = (c >> 2) & 1, hh = c & 3;
          bf16* base = b == 0 ? g_k : (b == 1 ? g_v : g_q);
          const int row = r0 + 8 * e;
          const int pos = b == 2 ? q : (q ^ (((row >> 2) & 1) << 1));
          const int i = ((b + 1) % 3) * 16 + hh * 4 + e;
          *(uint2*)(base + ((size_t)(nb * 4 + hh) * S_ + row) * 16 + pos * 4) = make_uint2(pq[i], pq[i + 2]);
        }
      }
      if (k == 10 || k == 11) {
        const int t = k - 10;
        float nn[8];
        #pragma unroll
        for (int i = 0; i < 8; i++) {
          const uint32_t u = pq[t * 16 + (i >> 1) * 4 + (i & 1)], w = pq[t * 16 + (i >> 1) * 4 + (i & 1) + 2];
          nn[i] = fmaf(bf_lo(u), bf_lo(u), fmaf(bf_hi(u), bf_hi(u), fmaf(bf_lo(w), bf_lo(w), bf_hi(w) * bf_hi(w))));
        }
        #pragma unroll
        for (int i = 0; i < 8; i++) nn[i] += __shfl_xor_sync(0xffffffffu, nn[i], 1);
        #pragma unroll
        for (int i = 0; i < 8; i++) nn[i] += __shfl_xor_sync(0xffffffffu, nn[i], 2);
        #pragma unroll
        for (int i = 0; i < 4; i++) {
          const uint32_t m = __reduce_max_sync(0xffffffffu, max(__float_as_uint(nn[2 * i]) & 0x7fffffffu, __float_as_uint(nn[2 * i + 1]) & 0x7fffffffu));
          if (lane == 4 * t + i) mine = m;
        }
        if (t == 1 && lane < 8) g_kn[(nb * 128 + mb * 8 + wg * 4 + warp) * 8 + lane] = mine;
        if (t == 1) asm volatile("bar.arrive 3, 384;" ::: "memory");
      }
    }
    WG_WAIT(0);
    fence_regs(za); fence_regs(zb);
    if (lane == 0) mbar_arrive(sb + B_ADONE);
    float az[112];
    #pragma unroll
    for (int i = 0; i < 112; i++) az[i] = i < 64 ? za[i] : zb[i - 64];
    bf16* z1row = g_z1 + (size_t)r0 * FH + (a1 - n2) * 32 + q * 8;
    bf16* z2row = g_z2n + (size_t)r0 * FH + a2 * 32 + q * 8;
    const float k1a = 0.7978845608f * rs0, k3a = 0.7978845608f * 0.044715f * rs0 * rs0 * rs0, kha = 0.5f * rs0;
    const float k1b = 0.7978845608f * rs1, k3b = 0.7978845608f * 0.044715f * rs1 * rs1 * rs1, khb = 0.5f * rs1;
    #pragma unroll
    for (int i = 0; i < 64; i += 4) {
      az[i] = gelu2(az[i], k1a, k3a); az[i + 1] = gelu2(az[i + 1], k1a, k3a);
      az[i + 2] = gelu2(az[i + 2], k1b, k3b); az[i + 3] = gelu2(az[i + 3], k1b, k3b);
    }
    {
      float sa = 0.f, sb2 = 0.f, ta = 0.f, tb = 0.f;
      #pragma unroll
      for (int i = 0; i < 48; i += 4) { sa += az[i] + az[i + 1]; sb2 += az[i + 2] + az[i + 3]; }
      #pragma unroll
      for (int i = 48; i < 64; i += 4) { ta += az[i] + az[i + 1]; tb += az[i + 2] + az[i + 3]; }
      if (n2 == 4) { sa += ta; sb2 += tb; }
      sa += __shfl_xor_sync(0xffffffffu, sa, 1); sb2 += __shfl_xor_sync(0xffffffffu, sb2, 1);
      sa += __shfl_xor_sync(0xffffffffu, sa, 2); sb2 += __shfl_xor_sync(0xffffffffu, sb2, 2);
      const float inv = n2 == 4 ? 1.f / 128 : 1.f / 96;
      const float ma = sa * inv, mb2 = sb2 * inv;
      sa = 0.f; sb2 = 0.f; ta = 0.f; tb = 0.f;
      #pragma unroll
      for (int i = 0; i < 48; i += 4) {
        const float d0 = az[i] - ma, d1 = az[i + 1] - ma, d2 = az[i + 2] - mb2, d3 = az[i + 3] - mb2;
        sa = fmaf(d0, d0, sa); ta = fmaf(d1, d1, ta); sb2 = fmaf(d2, d2, sb2); tb = fmaf(d3, d3, tb);
      }
      if (n2 == 4) {
        #pragma unroll
        for (int i = 48; i < 64; i += 4) {
          const float d0 = az[i] - ma, d1 = az[i + 1] - ma, d2 = az[i + 2] - mb2, d3 = az[i + 3] - mb2;
          sa = fmaf(d0, d0, sa); ta = fmaf(d1, d1, ta); sb2 = fmaf(d2, d2, sb2); tb = fmaf(d3, d3, tb);
        }
      }
      sa += ta; sb2 += tb;
      sa += __shfl_xor_sync(0xffffffffu, sa, 1); sb2 += __shfl_xor_sync(0xffffffffu, sb2, 1);
      sa += __shfl_xor_sync(0xffffffffu, sa, 2); sb2 += __shfl_xor_sync(0xffffffffu, sb2, 2);
      if (q < 2)
        asm volatile("{\n.reg .b64 t;\nmov.b64 t, {%1, %2};\nst.relaxed.gpu.global.b64 [%0], t;\n}" ::"l"(g_st + nb * S_ + r0 + 8 * q),
                     "r"(__float_as_uint(q ? mb2 * khb : ma * kha)), "r"(__float_as_uint(q ? sb2 * khb * khb : sa * kha * kha) | 0x80000000u) : "memory");
      if (q >= 2) g_kh[blockIdx.x * 128 + lr + 8 * (q & 1)] = (q & 1) ? khb : kha;
      #pragma unroll
      for (int i = 64; i < 112; i++) asm volatile("" : "+f"(az[i])::"memory");
    }
    float2 pst[4];
    auto ld_st = [&]() {
      #pragma unroll
      for (int i = 0; i < 4; i++)
        asm volatile("{\n.reg .b64 t;\nld.relaxed.gpu.global.b64 t, [%2];\nmov.b64 {%0, %1}, t;\n}" : "=f"(pst[i].x), "=f"(pst[i].y) : "l"(g_st + (2 * q + (i & 1)) * S_ + r0 + 8 * (i >> 1)) : "memory");
    };
    #pragma unroll
    for (int b = 3; b < 7; b++) {
      if (b > 3) {
        #pragma unroll
        for (int i = 16 * b; i < 16 * b + 16; i += 4) {
          az[i] = gelu2(az[i], k1a, k3a); az[i + 1] = gelu2(az[i + 1], k1a, k3a);
          az[i + 2] = gelu2(az[i + 2], k1b, k3b); az[i + 3] = gelu2(az[i + 3], k1b, k3b);
        }
      }
      if (b == 6) ld_st();
      if (b > 3 || n2 == 3) {
        #pragma unroll
        for (int e = 0; e < 2; e++)
          *(uint4*)(z1row + e * 8 * FH + b * 32) = make_uint4(pack_bf16(az[16 * b + 2 * e], az[16 * b + 2 * e + 1]), pack_bf16(az[16 * b + 4 + 2 * e], az[16 * b + 5 + 2 * e]),
                                                              pack_bf16(az[16 * b + 8 + 2 * e], az[16 * b + 9 + 2 * e]), pack_bf16(az[16 * b + 12 + 2 * e], az[16 * b + 13 + 2 * e]));
      }
    }
    #pragma unroll 1
    for (int it = 0; it < (1 << 22); it++) {
      if ((int)(__float_as_uint(pst[0].y) & __float_as_uint(pst[1].y) & __float_as_uint(pst[2].y) & __float_as_uint(pst[3].y)) < 0) break;
      __nanosleep(50);
      ld_st();
    }
    __syncwarp();
    first_q(sb, tid, wg, qn);
    #pragma unroll
    for (int e = 0; e < 2; e++) {
      const float4 p = make_float4(pst[2 * e].x, -pst[2 * e].y, pst[2 * e + 1].x, -pst[2 * e + 1].y);
      float m = p.x * (128.f / FH) + p.z * (96.f / FH);
      m += __shfl_xor_sync(0xffffffffu, m, 1); m += __shfl_xor_sync(0xffffffffu, m, 2);
      float v = p.y + p.w + 128.f * (p.x - m) * (p.x - m) + 96.f * (p.z - m) * (p.z - m);
      v += __shfl_xor_sync(0xffffffffu, v, 1); v += __shfl_xor_sync(0xffffffffu, v, 2);
      const float rs = rstd_bf(v * (1.f / FH));
      const float c = -round_bf(m) * rs, rk = rs * (e ? khb : kha);
      #pragma unroll
      for (int b = 0; b < 4; b++) {
        if (b < 3 || n2 == 4) {
          uint32_t w[4];
          #pragma unroll
          for (int j = 0; j < 4; j++) w[j] = pack_bf16(fmaf(az[16 * b + 4 * j + 2 * e], rk, c), fmaf(az[16 * b + 4 * j + 2 * e + 1], rk, c));
          *(uint4*)(z2row + e * 8 * FH + b * 32) = make_uint4(w[0], w[1], w[2], w[3]);
        }
      }
    }
    asm volatile("bar.arrive 4, 288;" ::: "memory");
}

__device__ __forceinline__ void publish_o(int head, int qb, int t, int n, int lane, uint32_t add) {
  if (lane < n) {
    asm volatile("fence.proxy.async.global;" ::: "memory");
    asm volatile("red.release.gpu.global.add.u32 [%0], %1;" ::"l"(g_cnt + (17 + qb * 8 + ((t + 3 * lane + (head >> 2)) & 7)) * 32 + (head >> 2)), "r"(add) : "memory");
  }
  __syncwarp();
}
__device__ __forceinline__ void chain_b(const Maps& tm, const bf16* __restrict__ bias, uint32_t sb, int tid, int mb, int nb, uint32_t tag) {
    const int lane = tid & 31;
    const int uw = __shfl_sync(0xffffffffu, tid >> 5, 0);
    const uint32_t full = sb + B_FULL2;
    const CUtensorMap* m_sp = uw == 0 ? &tm.wsp : &tm.z2n;
    const uint32_t dst_sp = sb + RING + (uw == 0 ? 0 : 8192 + uw * 8192);
    int c0 = uw == 0 ? 0 : nb * 112 + (uw - 1) * 64, c1 = uw == 0 ? mb * 128 : 0;
    const int dc0 = uw == 0 ? 64 : 0, dc1 = 64 - dc0;
    auto fill_sp = [&](int st) {
      if (uw == 3) mbar_expect_e(full + 8 * st, 32768);
      else tma2d_e(dst_sp + st * SB, m_sp, c0, c1, full + 8 * st);
      c0 += dc0; c1 += dc1;
    };
    if (uw == 1 || uw == 2) flags_wait_warp<128>(g_fz, tag, lane);
    fill_sp(0); fill_sp(1);
    const int warp = tid >> 5, q = lane & 3;
    const int lrow = (lane & 7) + ((lane >> 3) & 1) * 8;
    const int s = 2; const uint32_t ph = 0;
    const int orow = mb * 128 + (nb & 1) * 64, ocol = (nb >> 1) * 128;
    uint32_t xv[2][16];
    {
      float bv[4], kv[4];
      #pragma unroll
      for (int i = 0; i < 4; i++) {
        const int lr = (i >> 1) * 64 + warp * 16 + (lane >> 2) + (i & 1) * 8;
        kv[i] = __ldcg(g_kh + blockIdx.x * 128 + lr);
        bv[i] = __bfloat162float(bias[mb * 128 + lr]) * kv[i];
      }
      float acc[2][56];
      #pragma unroll
      for (int i = 0; i < 56; i++) { acc[0][i] = 0.f; acc[1][i] = 0.f; }
      fence_regs(acc[0]); fence_regs(acc[1]);
      const uint64_t da0 = desc_a(sb + RING);
      auto step = [&](int st, uint32_t par, auto refill) {
        const uint64_t da = da0 + st * (SB >> 4), db = da + (((uint64_t)511 << 16) + 1024);
        mbar_wait(full + 8 * st, par);
        WG_FENCE();
        #pragma unroll
        for (int j = 0; j < 4; j++) {
          wgmma_ss<112>(acc[0], da + j * 2, db + j * 128, 1);
          wgmma_ss<112>(acc[1], da + 512 + j * 2, db + j * 128, 1);
          if (j == 1) {
            WG_COMMIT();
            asm volatile("bar.sync 5, 128;" ::: "memory");
            refill();
            WG_WAIT(0); WG_FENCE();
          }
        }
        WG_COMMIT();
        WG_WAIT(0);
      };
      #pragma unroll 1
      for (int i = 0;; i++) {
        step(0, i & 1, [&]() {
          if (i < 10) fill_sp(2);
          else if (uw == 3) mbar_expect_e(full + 16, 32768);
          else if (uw != 0) tma2d_e(sb + RING + 2 * SB + (uw - 1) * 16384, &tm.z1, nb * 112 + (uw - 1) * 64, mb * 128, full + 16);
        });
        step(1, i & 1, [&]() {
          if (i < 10) fill_sp(0);
          else if (uw == 3) mbar_expect_e(full, 16384);
          else if (uw != 0) tma2d_e(sb + RING + (uw - 1) * 8192, &tm.x, ocol + (uw - 1) * 64, orow, full);
        });
        if (i == 10) break;
        step(2, i & 1, [&]() { fill_sp(1); });
      }
      fence_regs(acc[0]); fence_regs(acc[1]);
      g_st[blockIdx.x * 128 + tid] = make_float2(0.f, 0.f);
      mbar_wait(full + 8 * s, ph);
      #pragma unroll
      for (int h = 0; h < 2; h++) {
        const int r0 = mb * 128 + h * 64 + warp * 16 + (lane >> 2);
        const float b0 = bv[2 * h], b1 = bv[2 * h + 1], k0 = kv[2 * h], k1 = kv[2 * h + 1];
        uint32_t u0[14], u1[14];
        const uint32_t zb = sb + RING + s * SB + (h * 64 + warp * 16 + lrow) * 128;
        #pragma unroll
        for (int j = 0; j < 14; j += 2) {
          uint32_t z0, z1, z2, z3;
          const int c = j + (lane >> 4);
          ldsm4(z0, z1, z2, z3, zb + (j >> 3) * 16384 + (((c & 7) ^ (lane & 7)) << 4));
          const float* a = &acc[h][4 * j];
          u0[j] = hmul2_bf(z0, pack_bf16(fmaf(a[0], k0, b0), fmaf(a[1], k0, b0)));
          u1[j] = hmul2_bf(z1, pack_bf16(fmaf(a[2], k1, b1), fmaf(a[3], k1, b1)));
          u0[j + 1] = hmul2_bf(z2, pack_bf16(fmaf(a[4], k0, b0), fmaf(a[5], k0, b0)));
          u1[j + 1] = hmul2_bf(z3, pack_bf16(fmaf(a[6], k1, b1), fmaf(a[7], k1, b1)));
        }
        bf16* d0 = g_u + (size_t)r0 * FH + nb * 112 + q * 8;
        bf16* d1 = d0 + 8 * FH;
        if (nb & 1) {
          *(uint2*)(d0 - 12) = make_uint2(u0[0], u0[1]); *(uint2*)(d1 - 12) = make_uint2(u1[0], u1[1]);
          #pragma unroll
          for (int b = 0; b < 3; b++) {
            *(uint4*)(d0 + 16 + 32 * b) = make_uint4(u0[2 + 4 * b], u0[3 + 4 * b], u0[4 + 4 * b], u0[5 + 4 * b]);
            *(uint4*)(d1 + 16 + 32 * b) = make_uint4(u1[2 + 4 * b], u1[3 + 4 * b], u1[4 + 4 * b], u1[5 + 4 * b]);
          }
        } else {
          #pragma unroll
          for (int b = 0; b < 3; b++) {
            *(uint4*)(d0 + 32 * b) = make_uint4(u0[4 * b], u0[1 + 4 * b], u0[2 + 4 * b], u0[3 + 4 * b]);
            *(uint4*)(d1 + 32 * b) = make_uint4(u1[4 * b], u1[1 + 4 * b], u1[2 + 4 * b], u1[3 + 4 * b]);
          }
          *(uint2*)(d0 + 96) = make_uint2(u0[12], u0[13]); *(uint2*)(d1 + 96) = make_uint2(u1[12], u1[13]);
        }
      }
      __syncwarp();
      {
        uint32_t n = 0;
        if (uw == 3) {
          asm volatile("ld.volatile.shared.u32 %0, [%1];" : "=r"(n) : "r"(sb + B_GUARD));
          n = n ? 0 : 4;
          if (n) asm volatile("bar.sync 6, 416;" ::: "memory");
        }
        if (lane <= n) {
          const int kbh = blockIdx.x >> 4;
          uint32_t* p = lane == n ? g_cnt + (1 + mb) * 32 : g_cnt + (17 + (blockIdx.x & 3) * 8 + ((lane + kbh) & 7)) * 32 + kbh;
          asm volatile("fence.proxy.async.global;" ::: "memory");
          asm volatile("red.release.gpu.global.add.u32 [%0], %1;" ::"l"(p), "r"(lane == n ? 1 : 4) : "memory");
        }
        __syncwarp();
      }
      mbar_wait(full, ph ^ 1);
      #pragma unroll
      for (int h = 0; h < 2; h++) {
        #pragma unroll
        for (int i = 0; i < 4; i++)
          ldsm4(xv[h][4 * i], xv[h][4 * i + 1], xv[h][4 * i + 2], xv[h][4 * i + 3],
                sb + RING + h * 8192 + (warp * 16 + lrow) * 128 + (((2 * i + (lane >> 4)) ^ (lane & 7)) << 4));
      }
      asm volatile("fence.proxy.async.shared::cta;" ::: "memory");
      asm volatile("bar.sync 5, 128;" ::: "memory");
    }
    const uint32_t full3 = sb + B_FULL3;
    const CUtensorMap* m_out = uw == 0 ? &tm.u : &tm.wout;
    const uint32_t dst_w = sb + RING + uw * 8192;
    c0 = uw == 0 ? 0 : ocol + (uw - 1) * 64; c1 = uw == 0 ? orow : 0;
    auto fill_out = [&](int st) {
      if (uw == 3) mbar_expect_e(full3 + 8 * st, SB3);
      else tma2d_e(dst_w + st * SB3, m_out, c0, c1, full3 + 8 * st);
      c0 += dc0; c1 += dc1;
    };
    if (uw == 0) {
      if (lane == 0) flag_wait(g_cnt + (1 + mb) * 32, tag * 32);
      __syncwarp();
      asm volatile("fence.proxy.async.global;" ::: "memory");
    }
    #pragma unroll 1
    for (int n = 0; n < 4; n++) fill_out(n);
    const uint64_t d3 = desc_a(sb + RING);
    uint32_t gp[32];
    float sv[64];
    #pragma unroll
    for (int i = 0; i < 64; i++) sv[i] = 0.f;
    fence_regs(sv);
    auto ostep = [&](int st, uint32_t par, bool refill) {
      const uint64_t da = d3 + (uint64_t)(st * (SB3 >> 4)), db = da + (((uint64_t)511 << 16) + 512);
      mbar_wait(full3 + 8 * st, par);
      WG_FENCE();
      #pragma unroll
      for (int j = 0; j < 4; j++) wgmma_ss<128>(sv, da + j * 2, db + j * 128, 1);
      WG_COMMIT();
      WG_WAIT(1);
      asm volatile("bar.sync 5, 128;" ::: "memory");
      if (refill) fill_out((st + 3) & 3);
    };
    #pragma unroll 1
    for (int i = 0;; i++) {
      ostep(0, i & 1, i == 1 || i == 2);
      ostep(1, i & 1, i < 3);
      if (i == 3) break;
      ostep(2, i & 1, true);
      ostep(3, i & 1, i < 2);
    }
    WG_WAIT(0);
    asm volatile("bar.sync 5, 128;" ::: "memory");
    if (uw == 3) mbar_expect_e(sb + B_WOB, 8 * 16384);
    else {
      tma3d_e(sb + RING + uw * 32768, &tm.wo, 0, uw * 128, ocol >> 6, sb + B_WOB);
      tma3d_e(sb + RING + uw * 32768 + 16384, &tm.wo, 0, uw * 128 + 64, ocol >> 6, sb + B_WOB);
    }
    fence_regs(sv);
    #pragma unroll
    for (int j = 0; j < 32; j++) {
      const float y0 = sv[2 * j], y1 = sv[2 * j + 1];
      gp[j] = pack_bf16(y0 * rcpf(1.f + ex2f(-1.4426950408889634f * y0)), y1 * rcpf(1.f + ex2f(-1.4426950408889634f * y1)));
      sv[2 * j] = 0.f; sv[2 * j + 1] = 0.f;
    }
    fence_regs(gp); fence_regs(sv);
    if (uw == 1) {
      mbar_wait(sb + B_KVFREE, 0);
      tma3d_e(sb + 65536, &tm.wo, 0, 384, ocol >> 6, sb + B_WOB);
      tma3d_e(sb + 81920, &tm.wo, 0, 448, ocol >> 6, sb + B_WOB);
    }
    #pragma unroll 1
    for (int n = 0; n < 8; n++) {
      if (n == 0) mbar_wait(sb + B_WOB, 0);
      const int kb = ((orow >> 6) - n) & 7;
      mbar_wait(sb + B_X + 8 * kb, 1);
      const uint64_t da = desc_a(sb + kb * 8192), db = desc_b(sb + (kb < 6 ? RING + kb * 16384 : kb * 16384 - 32768));
      WG_FENCE();
      #pragma unroll
      for (int j = 0; j < 4; j++) wgmma_ss<128>(sv, da + j * 2, db + j * 128, 1);
      WG_COMMIT();
    }
    WG_WAIT(0);
    fence_regs(sv);
    #pragma unroll
    for (int h = 0; h < 2; h++) {
      const uint32_t xt = sb + 98304 + h * 8192 + warp * 2048;
      #pragma unroll
      for (int i = 0; i < 4; i++) {
        uint32_t w[4];
        #pragma unroll
        for (int j = 0; j < 4; j++)
          w[j] = hfma2_bf(pack_bf16(sv[32 * h + 8 * i + 2 * j], sv[32 * h + 8 * i + 2 * j + 1]), gp[16 * h + 4 * i + j], xv[h][4 * i + j]);
        stsm4(xt + lrow * 128 + (((2 * i + (lane >> 4)) ^ (lane & 7)) << 4), w[0], w[1], w[2], w[3]);
      }
      asm volatile("fence.proxy.async.shared::cta;" ::: "memory");
      __syncwarp();
      if (lane == 0) {
        tma2d_store(&tm.out, xt, ocol + h * 64, orow + warp * 16);
        asm volatile("cp.async.bulk.commit_group;" ::: "memory");
      }
    }
    if (lane == 0) asm volatile("cp.async.bulk.wait_group.read 0;" ::: "memory");
}

__device__ __forceinline__ uint32_t exp2_mufu(float a, float b) { return pack_bf16(ex2f(a), ex2f(b)); }
constexpr float EXP_BIAS = 382.401f;
__device__ __forceinline__ uint32_t exp2_soft(float ta, float tb, uint32_t mask) {
  const uint32_t u = __byte_perm(__float_as_uint(ta), __float_as_uint(tb), 0x6521);
  uint32_t g, e, r;
  asm("lop3.b32 %0, %1, %2, 0xBF00BF00, 0xEA;" : "=r"(g) : "r"(u), "r"(mask));
  asm("lop3.b32 %0, %1, %2, 0x80038003, 0x9A;" : "=r"(e) : "r"(u), "r"(mask));
  asm("fma.rn.bf16x2 %0, %1, %2, %3;" : "=r"(r) : "r"(u), "r"(g), "r"(e));
  return r;
}
constexpr int NSOFT = 10;
__device__ __forceinline__ void init_bias(float (&ss)[2 * NSOFT], uint32_t addr) {
  #pragma unroll
  for (int i = 0; i < 2 * NSOFT; i += 4)
    asm volatile("ld.volatile.shared.v4.f32 {%0,%1,%2,%3}, [%4];" : "=f"(ss[i]), "=f"(ss[i + 1]), "=f"(ss[i + 2]), "=f"(ss[i + 3]) : "r"(addr));
}
__device__ __forceinline__ void exp_tile(float (&ss)[2 * NSOFT], float (&sm)[32 - 2 * NSOFT], uint32_t (&p)[16], uint32_t baddr) {
  fence_regs(ss); fence_regs(sm);
  #pragma unroll
  for (int i = 0; i < NSOFT; i++) p[i] = exp2_soft(ss[2 * i], ss[2 * i + 1], 0x007F007Fu);
  init_bias(ss, baddr);
  #pragma unroll
  for (int i = NSOFT; i < 16; i++) p[i] = exp2_mufu(sm[2 * (i - NSOFT)], sm[2 * (i - NSOFT) + 1]);
  fence_regs(p); fence_regs(ss);
}
constexpr float SAFE_LOG2 = 64.f;
constexpr uint64_t VSTEP = (uint64_t)32 - ((uint64_t)32 << 16);

__device__ __forceinline__ void store_o(const float (&o)[12], int row, int head, int lane) {
  const float i0 = rcpf(o[8]), i1 = rcpf(o[10]);
  const bool hi = lane & 2;
  const uint32_t a0 = pack_bf16(o[0] * i0, o[1] * i0), a1 = pack_bf16(o[4] * i0, o[5] * i0);
  const uint32_t b0 = pack_bf16(o[2] * i1, o[3] * i1), b1 = pack_bf16(o[6] * i1, o[7] * i1);
  const uint32_t ax = __shfl_xor_sync(0xffffffffu, hi ? a0 : a1, 2), bx = __shfl_xor_sync(0xffffffffu, hi ? b0 : b1, 2);
  uint2* op = (uint2*)(g_o + (size_t)row * D_ + head * 16) + 2 * (lane & 1) + (hi ? 1 : 0);
  op[0] = hi ? make_uint2(ax, a1) : make_uint2(a0, ax);
  op[8 * 128] = hi ? make_uint2(bx, b1) : make_uint2(b0, bx);
}
template <int MODE>
__device__ __forceinline__ void attn_tile(uint32_t sb, int tid, int head, int rbase, int tile, int tnext, uint32_t (&qn)[4], const uint32_t* qp,
                                          bool first) {
  const int rot = head >> 2;
  constexpr int IT0 = MODE == 2 ? 8 : 0, NA = MODE == 0 ? 4 : 1, NB = MODE == 0 ? 4 : 8;
  const uint32_t full = sb + B_KV, sd = sb & 0x3FFFF;
  constexpr uint64_t KO = AT_V >> 4;
  uint64_t vd = (((uint64_t)((AT_ONES - AT_V) >> 4) << 16) | ((uint64_t)16 << 32) | ((uint64_t)3 << 62) | (uint64_t)((sd + AT_V) >> 4)) + VSTEP * 8 * IT0;
  const uint32_t baddr = sb + B_BIAS;
  uint32_t qf[4] = {qn[0], qn[1], qn[2], qn[3]};
  float o[12], ss[2 * NSOFT], sm[32 - 2 * NSOFT];
  uint32_t p0[16], p1[16];
  float4* part = g_part + blockIdx.x * 384 + (tid & 127);
  if (MODE == 2) {
    asm volatile("bar.sync 8, 256;" ::: "memory");
    #pragma unroll
    for (int i = 0; i < 3; i++) { const float4 v = __ldcg(part + i * 128); o[4 * i] = v.x; o[4 * i + 1] = v.y; o[4 * i + 2] = v.z; o[4 * i + 3] = v.w; }
  } else {
    if (MODE == 0 && tile >= 4) asm volatile("bar.arrive 6, 416;" ::: "memory");
    #pragma unroll
    for (int i = 0; i < 12; i++) o[i] = 0.f;
  }
  #pragma unroll
  for (int i = 0; i < 32 - 2 * NSOFT; i++) sm[i] = 0.f;
  init_bias(ss, baddr);
  fence_regs(ss); fence_regs(sm); fence_regs(o); fence_regs(qf);
  WG_FENCE(); wgmma_qk_acc(ss, qf, vd - KO); wgmma_qk(sm, qf, vd - (KO - 8 * NSOFT)); WG_COMMIT();
  WG_WAIT(0);
  if (MODE != 2) { const uint32_t* p = qp + ((tnext + rot) & 7) * 512; qn[0] = __ldcg(p); qn[1] = __ldcg(p + 64); qn[2] = __ldcg(p + 4); qn[3] = __ldcg(p + 68); }
  if (MODE == 1) { mbar_wait_u(full, 0); mbar_wait_u(full + 8, 0); }
  #pragma unroll 1
  for (int g = 0; g < NA; g++) {
    if (MODE == 0) {
      if (first) mbar_wait_u(full + 8 * g, 0);
    }
    int i = 0;
    #pragma unroll 1
    do {
      exp_tile(ss, sm, p0, baddr);
      WG_FENCE(); wgmma_qk_acc(ss, qf, vd - (KO - 128)); wgmma_qk(sm, qf, vd - (KO - 128 - 8 * NSOFT)); WG_COMMIT();
      #pragma unroll
      for (int k = 0; k < 4; k++) wgmma_pv(o, p0[4 * k], p0[4 * k + 1], p0[4 * k + 2], p0[4 * k + 3], vd + VSTEP * k);
      WG_COMMIT(); WG_WAIT(1);
      exp_tile(ss, sm, p1, baddr);
      WG_FENCE(); wgmma_qk_acc(ss, qf, vd - (KO - 256)); wgmma_qk(sm, qf, vd - (KO - 256 - 8 * NSOFT)); WG_COMMIT();
      #pragma unroll
      for (int k = 0; k < 4; k++) wgmma_pv(o, p1[4 * k], p1[4 * k + 1], p1[4 * k + 2], p1[4 * k + 3], vd + VSTEP * (4 + k));
      WG_COMMIT(); WG_WAIT(1);
      vd += VSTEP * 8;
    } while (++i < NB);
  }
  WG_WAIT(0);
  fence_regs(o);
  if (MODE == 1) {
    #pragma unroll
    for (int i = 0; i < 3; i++) part[i * 128] = make_float4(o[4 * i], o[4 * i + 1], o[4 * i + 2], o[4 * i + 3]);
    asm volatile("bar.arrive 8, 256;" ::: "memory");
  } else {
    store_o(o, rbase + ((tile + rot) & 7) * 64, head, tid & 31);
  }
  __syncwarp();
}

__device__ __forceinline__ void attention(uint32_t sb, int tid, int wg, int head, int qb, uint32_t (&qn)[4]) {
  const int lane = tid & 31, warp = (tid >> 5) & 3;
  const uint32_t full = sb + B_KV;
  const int rbase = qb * 512 + warp * 16 + (lane >> 2);
  const uint32_t* qp = (const uint32_t*)(g_q + ((size_t)head * S_ + rbase) * 16) + (lane & 3);
  uint32_t unsafe;
  asm volatile("ld.volatile.shared.u32 %0, [%1];" : "=r"(unsafe) : "r"(sb + B_GUARD));
  unsafe = __shfl_sync(0xffffffffu, unsafe, 0);
  const uint32_t sd = sb & 0x3FFFF;
  const uint64_t kd0 = ((uint64_t)1 << 16) | ((uint64_t)16 << 32) | ((uint64_t)3 << 62) | (uint64_t)(sd >> 4);
  const uint64_t vd0 = ((uint64_t)((AT_ONES - AT_V) >> 4) << 16) | ((uint64_t)16 << 32) | ((uint64_t)3 << 62) | (uint64_t)((sd + AT_V) >> 4);
  uint32_t* const ocnt = g_cnt + (17 + qb * 8) * 32 + (head >> 2);
  {
    if (!unsafe) {
     const int t0 = 2 - wg;
     mbar_wait_u(full + 32, 0);
     if (wg == 0) attn_tile<1>(sb, tid, head, rbase, 7, 2, qn, qp, false);
     #pragma unroll 1
     for (int i = 0; i < (wg == 2 ? 3 : 2); i++) attn_tile<0>(sb, tid, head, rbase, t0 + 3 * i, (t0 + 3 * i + 3) & 7, qn, qp, i == 0);
     if (wg == 1) attn_tile<2>(sb, tid, head, rbase, 7, 0, qn, qp, false);
     mbar_arrive_e(sb + B_KVFREE);
     if (tid >= 256 && tid < 288) asm volatile("bar.arrive 7, 64;" ::: "memory");
     else {
       const bool two = tid >= 288 && tid < 320;
       if (two) asm volatile("bar.sync 7, 64;" ::: "memory");
       publish_o(head, qb, wg == 0 ? 5 : (wg == 1 ? 4 : 6), wg == 1 ? 2 : 1, lane, two ? 2 : 1);
     }
    } else {
     mbar_wait_u(full + 32, 0);
     #pragma unroll 1
     for (int tile = 2 - wg; tile < 8; tile += 3) {
      const uint32_t* p = qp + tile * 512;
      uint32_t qf[4] = {__ldcg(p), __ldcg(p + 64), __ldcg(p + 4), __ldcg(p + 68)};
      float o[12], s[32];
      uint32_t p0[16];
      #pragma unroll
      for (int i = 0; i < 32; i++) s[i] = 0.f;
      #pragma unroll
      for (int i = 0; i < 12; i++) o[i] = 0.f;
      float m0 = -INFINITY, m1 = -INFINITY;
      uint64_t kd = kd0, vd = vd0;
      #pragma unroll 1
      for (int g = 0; g < 4; g++) {
        mbar_wait_u(full + 8 * g, 0);
        #pragma unroll 1
        for (int it = 0; it < 8; it++) {
          WG_FENCE(); wgmma_qk(s, qf, kd); WG_COMMIT(); WG_WAIT(0); fence_regs(s); fence_regs(o);
          float n0 = m0, n1 = m1;
          #pragma unroll
          for (int j = 0; j < 8; j++) { n0 = fmaxf(n0, fmaxf(s[4 * j], s[4 * j + 1])); n1 = fmaxf(n1, fmaxf(s[4 * j + 2], s[4 * j + 3])); }
          n0 = fmaxf(n0, __shfl_xor_sync(0xffffffffu, n0, 1)); n0 = fmaxf(n0, __shfl_xor_sync(0xffffffffu, n0, 2));
          n1 = fmaxf(n1, __shfl_xor_sync(0xffffffffu, n1, 1)); n1 = fmaxf(n1, __shfl_xor_sync(0xffffffffu, n1, 2));
          const float c0 = ex2f(m0 - n0), c1 = ex2f(m1 - n1);
          m0 = n0; m1 = n1;
          #pragma unroll
          for (int j = 0; j < 3; j++) { o[4 * j] *= c0; o[4 * j + 1] *= c0; o[4 * j + 2] *= c1; o[4 * j + 3] *= c1; }
          #pragma unroll
          for (int j = 0; j < 8; j++) {
            p0[2 * j] = exp2_mufu(s[4 * j] - n0, s[4 * j + 1] - n0);
            p0[2 * j + 1] = exp2_mufu(s[4 * j + 2] - n1, s[4 * j + 3] - n1);
          }
          fence_regs(p0); fence_regs(o);
          WG_FENCE();
          #pragma unroll
          for (int k = 0; k < 4; k++) wgmma_pv(o, p0[4 * k], p0[4 * k + 1], p0[4 * k + 2], p0[4 * k + 3], vd + VSTEP * k);
          WG_COMMIT();
          kd += 128; vd += VSTEP * 4;
        }
      }
      WG_WAIT(0);
      fence_regs(o);
      store_o(o, rbase + tile * 64, head, lane);
      __syncwarp();
      if (lane == 0) flag_add(ocnt + tile * 32);
      __syncwarp();
     }
     mbar_arrive_e(sb + B_KVFREE);
    }
  }
}

__global__ void __launch_bounds__(512, 1) k_fused(const __grid_constant__ Maps tm, const bf16* __restrict__ bias,
                                                  const bf16* __restrict__ wqkv, const bf16* __restrict__ w_in) {
  extern __shared__ __align__(1024) unsigned char smem[];
  const uint32_t sb = smem_u32(smem);
  const int tid = threadIdx.x, lane = tid & 31;
  const int wg = __shfl_sync(0xffffffffu, tid >> 7, 0);
  const int mb = ((blockIdx.x >> 4) << 1) | (blockIdx.x & 1), nb = (blockIdx.x >> 1) & 7;
  const int head = blockIdx.x >> 2, qb = blockIdx.x & 3;
  if (tid == 256) {
    for (int i = 0; i < 8; i++) mbar_init(sb + B_X + 8 * i, 1);
    asm volatile("fence.mbarrier_init.release.cluster;" ::: "memory");
    for (int i = 0; i < 2; i++) { mbar_expect(sb + B_X + 8 * i, 16384); tma2d(sb + i * 16384, &tm.x128, i * 64, mb * 128, sb + B_X + 8 * i); }
  } else if (tid == 288) {
    for (int i = 0; i < P1S; i++) { mbar_init(sb + B_FULL + 8 * i, 1); mbar_init(sb + B_EMPTY + 8 * i, 8); }
    asm volatile("fence.mbarrier_init.release.cluster;" ::: "memory");
  } else if (tid == 320) {
    for (int i = 0; i < ST; i++) mbar_init(sb + B_FULL2 + 8 * i, 1);
    for (int i = 0; i < 5; i++) mbar_init(sb + B_KV + 8 * i, 1);
    for (int i = 0; i < 4; i++) mbar_init(sb + B_FULL3 + 8 * i, 1);
    mbar_init(sb + B_GRD, 1); mbar_init(sb + B_WOB, 1); mbar_init(sb + B_KVFREE, 12); mbar_init(sb + B_ADONE, 8);
    asm volatile("fence.mbarrier_init.release.cluster;" ::: "memory");
  }
  if (tid < 128) ((uint32_t*)(smem + AT_ONES))[tid] = 0x3F803F80u;
  if (tid == 0) *(float4*)(smem + B_BIAS) = make_float4(EXP_BIAS, EXP_BIAS, EXP_BIAS, EXP_BIAS);
  asm volatile("fence.proxy.async.shared::cta;" ::: "memory");
  __syncthreads();
  if (wg == 3) {
    asm volatile("setmaxnreg.dec.sync.aligned.u32 24;");
    const uint32_t tag = __shfl_sync(0xffffffffu, *(volatile uint32_t*)&g_epoch + 1, 0);
    if (tid < 416) {
      if (lane == 0) {
        l2_prefetch((const char*)wqkv + (size_t)blockIdx.x * 12288, 12288);
        l2_prefetch((const char*)w_in + (size_t)blockIdx.x * 14336, 14336);
      }
      __syncwarp();
      asm volatile("bar.sync 3, 384;" ::: "memory");
      if (lane == 0) flag_set(g_fq + nb * 16 + mb, tag);
      __syncwarp();
      asm volatile("bar.sync 4, 288;" ::: "memory");
      if (lane == 0) flag_set(g_fz + mb * 8 + nb, tag);
      __syncwarp();
    } else if (tid < 448) {
        asm volatile("bar.sync 3, 384;" ::: "memory");
        flags_wait_warp<16>(g_fq + (head >> 2) * 16, tag, lane);
        const uint32_t full = sb + B_KV;
        const bf16 *kp = g_k + (size_t)head * S_ * 16, *vp = g_v + (size_t)head * S_ * 16;
        mbar_wait(sb + B_ADONE, 0);
        if (lane == 0) { mbar_expect(full + 32, 2048); bulk1d(sb, kp, 2048, full + 32); }
        #pragma unroll 1
        for (int g = 0; g < 4; g++) {
          if (lane == 0) {
            const int kbytes = g < 3 ? 16384 : 14336;
            mbar_expect(full + 8 * g, 16384 + kbytes);
            bulk1d(sb + 2048 + g * 16384, kp + 1024 + g * 8192, kbytes, full + 8 * g);
            bulk1d(sb + AT_V + g * 16384, vp + g * 8192, 16384, full + 8 * g);
          }
          __syncwarp();
        }
    } else if (tid < 480) {
        asm volatile("bar.sync 3, 384;" ::: "memory");
        flags_wait_warp<16>(g_fq + (head >> 2) * 16, tag, lane);
        const uint32_t* np = g_kn + ((head >> 2) * 128 + lane) * 8 + (head & 3);
        const uint4 v = make_uint4(__ldcg(np + 4), __ldcg(np + 260), __ldcg(np + 516), __ldcg(np + 772));
        const uint32_t w = __ldcg(np + qb * 256);
        const float kn2 = __uint_as_float(__reduce_max_sync(0xffffffffu, max(max(v.x, v.y), max(v.z, v.w))));
        const float qn2 = __uint_as_float(__reduce_max_sync(0xffffffffu, w));
        if (lane == 0) {
          *(volatile uint32_t*)(smem + B_TAG) = tag;
          *(volatile uint32_t*)(smem + B_GUARD) = !(qn2 * kn2 <= SAFE_LOG2 * SAFE_LOG2);
          mbar_arrive(sb + B_GRD);
        }
        __syncwarp();
    } else {
      asm volatile("bar.sync 3, 384;" ::: "memory");
    }
    asm volatile("bar.sync 5, 128;" ::: "memory");
    asm volatile("setmaxnreg.inc.sync.aligned.u32 176;");
    chain_b(tm, bias, sb, tid - 384, mb, nb, tag);
    if (blockIdx.x == 0 && tid == 384) g_epoch = tag;
  } else {
    uint32_t qn[4];
    if (wg == 2) {
      asm volatile("setmaxnreg.dec.sync.aligned.u32 112;");
      if (tid < 288) {
        {
          const int n2 = 4 - (nb & 1), a2 = (7 * nb + 1) >> 1, a1 = (7 * nb) >> 1;
          #pragma unroll 1
          for (int i = 2; i < 8; i++) { mbar_expect_e(sb + B_X + 8 * i, 16384); tma2d_e(sb + i * 16384, &tm.x128, i * 64, mb * 128, sb + B_X + 8 * i); }
          int s = 0; uint32_t ph = 1;
          #pragma unroll 1
          for (int k = 0; k < 32; k++) {
            mbar_wait(sb + B_EMPTY + 8 * s, ph);
            const uint32_t dst = sb + RING + s * P1B, bar = sb + B_FULL + 8 * s;
            if (k < 16) {
              mbar_expect_e(bar, 12288);
              tma3d_e(dst, &tm.wqkv, nb * 64, k * 32, 0, bar);
            } else {
              mbar_expect_e(bar, 14336);
              tma3d_e(dst, (nb & 1) ? &tm.win3 : &tm.win4, 0, (k - 16) * 32, 28 + a2, bar);
              tma3d_e(dst + n2 * 2048, (nb & 1) ? &tm.win4 : &tm.win3, 0, (k - 16) * 32, a1, bar);
            }
            if (++s == P1S) { s = 0; ph ^= 1; }
          }
        }
      }
      __syncwarp();
      first_q(sb, tid, wg, qn);
    } else {
      asm volatile("setmaxnreg.inc.sync.aligned.u32 184;");
      phase1(sb, tid, wg, mb, nb, qn);
      asm volatile("setmaxnreg.dec.sync.aligned.u32 112;");
    }
    __syncwarp();
    attention(sb, tid, wg, head, qb, qn);
    const int orow = mb * 128 + (nb & 1) * 64;
    if (tid >= 256 && tid < 288) {
      const uint32_t tag = *(volatile uint32_t*)(smem + B_TAG);
      uint32_t done = 0;
      int n = 0;
      #pragma unroll 1
      for (int it = 0; it < (1 << 22) && n < 8; it++) {
        uint32_t c = tag * 16 - 1;
        if (lane < 8) asm volatile("ld.acquire.gpu.global.u32 %0, [%1];" : "=r"(c) : "l"(g_cnt + (17 + (orow >> 6)) * 32 + (((orow >> 6) - lane) & 7)) : "memory");
        uint32_t rdy = __ballot_sync(0xffffffffu, (int)(c - tag * 16) >= 0) & ~done;
        asm volatile("fence.proxy.async.global;" ::: "memory");
        if (it == 0) mbar_wait(sb + B_KVFREE, 0);
        done |= rdy;
        #pragma unroll 1
        while (rdy) {
          const int kb = ((orow >> 6) + 1 - __ffs(rdy)) & 7;
          rdy &= rdy - 1;
          mbar_expect_e(sb + B_X + 8 * kb, 8192);
          tma2d_e(sb + kb * 8192, &tm.o, kb * 64, orow, sb + B_X + 8 * kb);
          n++;
        }
      }
    }
  }
}

typedef CUresult (*EncFn)(CUtensorMap*, CUtensorMapDataType, cuuint32_t, void*, const cuuint64_t*, const cuuint64_t*, const cuuint32_t*,
                          const cuuint32_t*, CUtensorMapInterleave, CUtensorMapSwizzle, CUtensorMapL2promotion, CUtensorMapFloatOOBfill);
static void make_map(EncFn enc, CUtensorMap* m, const void* p, int rows, int cols, int box_rows) {
  cuuint64_t dims[2] = {(cuuint64_t)cols, (cuuint64_t)rows};
  cuuint64_t str[1] = {(cuuint64_t)cols * 2};
  cuuint32_t box[2] = {64, (cuuint32_t)box_rows}, es[2] = {1, 1};
  enc(m, CU_TENSOR_MAP_DATA_TYPE_BFLOAT16, 2, (void*)p, dims, str, box, es, CU_TENSOR_MAP_INTERLEAVE_NONE,
      CU_TENSOR_MAP_SWIZZLE_128B, CU_TENSOR_MAP_L2_PROMOTION_L2_256B, CU_TENSOR_MAP_FLOAT_OOB_FILL_NONE);
}
static void make_map3(EncFn enc, CUtensorMap* m, const void* p, int d0, int d1, int d2, int s1, int s2, int b0, int b1, int b2) {
  cuuint64_t dims[3] = {(cuuint64_t)d0, (cuuint64_t)d1, (cuuint64_t)d2};
  cuuint64_t str[2] = {(cuuint64_t)s1, (cuuint64_t)s2};
  cuuint32_t box[3] = {(cuuint32_t)b0, (cuuint32_t)b1, (cuuint32_t)b2}, es[3] = {1, 1, 1};
  enc(m, CU_TENSOR_MAP_DATA_TYPE_BFLOAT16, 3, (void*)p, dims, str, box, es, CU_TENSOR_MAP_INTERLEAVE_NONE,
      b0 == 64 ? CU_TENSOR_MAP_SWIZZLE_128B : CU_TENSOR_MAP_SWIZZLE_64B, CU_TENSOR_MAP_L2_PROMOTION_L2_256B, CU_TENSOR_MAP_FLOAT_OOB_FILL_NONE);
}

extern "C" void kernel_launch(void* const* d_in, const int* in_sizes, int n_in, void* d_out, int out_size) {
  const bf16* x = (const bf16*)d_in[0];
  const bf16* wqkv = (const bf16*)d_in[1];
  const bf16* wo = (const bf16*)d_in[2];
  const bf16* w_in = (const bf16*)d_in[4];
  const bf16* w_sp = (const bf16*)d_in[5];
  const bf16* b_sp = (const bf16*)d_in[6];
  const bf16* w_out = (const bf16*)d_in[7];
  bf16* out = (bf16*)d_out;

  static EncFn enc = nullptr;
  static void *p_z, *p_o, *p_z2n, *p_u;
  if (!enc) {
    void* fn = nullptr; cudaDriverEntryPointQueryResult qr;
    cudaGetDriverEntryPoint("cuTensorMapEncodeTiled", &fn, cudaEnableDefault, &qr);
    enc = (EncFn)fn;
    cudaGetSymbolAddress(&p_z, g_z1); cudaGetSymbolAddress(&p_o, g_o); cudaGetSymbolAddress(&p_z2n, g_z2n); cudaGetSymbolAddress(&p_u, g_u);
    cudaFuncSetAttribute(k_fused, cudaFuncAttributeMaxDynamicSharedMemorySize, SMEM);
  }
  Maps tm;
  make_map3(enc, &tm.wqkv, wqkv, D_, D_, 3, 3 * D_ * 2, D_ * 2, 64, 32, 3);
  make_map3(enc, &tm.win4, w_in, 32, D_, 56, 2 * FH * 2, 64, 32, 32, 4);
  make_map3(enc, &tm.win3, w_in, 32, D_, 56, 2 * FH * 2, 64, 32, 32, 3);
  make_map(enc, &tm.x128, x, S_, D_, 128);
  make_map(enc, &tm.wsp, w_sp, S_, S_, 128);
  make_map(enc, &tm.z2n, p_z2n, S_, FH, 64);
  make_map(enc, &tm.z1, p_z, S_, FH, 128);
  make_map(enc, &tm.u, p_u, S_, FH, 64);
  make_map(enc, &tm.wout, w_out, FH, D_, 64);
  make_map(enc, &tm.o, p_o, S_, D_, 64);
  make_map3(enc, &tm.wo, wo, 64, D_, 8, D_ * 2, 128, 64, 64, 2);
  make_map(enc, &tm.x, x, S_, D_, 64);
  make_map(enc, &tm.out, out, S_, D_, 16);
  k_fused<<<128, 512, SMEM, cudaStreamPerThread>>>(tm, b_sp, wqkv, w_in);
}
```
